```python
import torch

def _softmax(x, axis=-1):
    return torch.softmax(x, dim=axis)

def _gelu(x):
    return torch.nn.functional.gelu(x, approximate='tanh')

def _silu(x):
    return torch.nn.functional.silu(x)

def _sigmoid(x):
    return torch.sigmoid(x)

def _layernorm(x, axis=-1, eps=1e-05):
    m = x.mean(dim=axis, keepdim=True)
    v = x.var(dim=axis, keepdim=True, unbiased=False)
    return (x - m) / torch.sqrt(v + eps)

def _scatter_add(tgt, idx, src, axis=0):
    return tgt.clone().index_add_(axis, idx, src)

def _segment_sum(src, seg, n):
    out = torch.zeros((n,) + src.shape[1:], dtype=src.dtype)
    return out.index_add_(0, seg, src)

def _pad(x, pw):
    flat = tuple((v for pair in reversed(pw) for v in pair))
    return torch.nn.functional.pad(x, flat)
kernel_name = 'gated_mix__grouped_kv_mqa__mixer_gmlp__prompt'

def setup_inputs():

    _w = lambda a: (lambda t: t.to(torch.bfloat16) if t.is_floating_point() else t)(torch.as_tensor(a))

    def _A_setup():
        B, S, D, H = (1, 2048, 640, 32)
        Dh = D // H
        return {'x': _w((lambda *s: torch.randn(*s, dtype=torch.bfloat16) * 0.05)(B, S, D)), 'wq': _w((lambda *s: torch.randn(*s, dtype=torch.bfloat16) * 1.6)(D, H * Dh)), 'wk': _w((lambda *s: torch.randn(*s, dtype=torch.bfloat16) * 1.6)(D, Dh)), 'wv': _w((lambda *s: torch.randn(*s, dtype=torch.bfloat16) * 0.2)(D, Dh)), 'wo': _w((lambda *s: torch.randn(*s, dtype=torch.bfloat16) * 0.2)(H * Dh, D))}
    _A_in = _A_setup()

    def _B_setup():
        B, S, D, F = (1, 2048, 640, 1728)
        Fh = F // 2
        return {'x': _w((lambda *s: torch.randn(*s, dtype=torch.bfloat16) * 0.05)(B, S, D)), 'w_in': _w((lambda *s: torch.randn(*s, dtype=torch.bfloat16) * 0.8)(D, 2 * Fh)), 'w_sp': _w(0.01 * (lambda *s: torch.randn(*s, dtype=torch.bfloat16) * 0.8)(S, S)), 'b_sp': _w(1.0 + 0.01 * (lambda *s: torch.randn(*s, dtype=torch.bfloat16) * 0.05)(S)), 'w_out': _w((lambda *s: torch.randn(*s, dtype=torch.bfloat16) * 0.05)(Fh, D))}
    _B_in = _B_setup()
    return {'A_x': _A_in['x'], 'A_wq': _A_in['wq'], 'A_wk': _A_in['wk'], 'A_wv': _A_in['wv'], 'A_wo': _A_in['wo'], 'B_x': _B_in['x'], 'B_w_in': _B_in['w_in'], 'B_w_sp': _B_in['w_sp'], 'B_b_sp': _B_in['b_sp'], 'B_w_out': _B_in['w_out'], 'gate_w': _w((lambda *s: torch.randn(*s, dtype=torch.bfloat16) * 0.05)(640) * 16.0)}

def reference(A_x, A_wq, A_wk, A_wv, A_wo, B_x, B_w_in, B_w_sp, B_b_sp, B_w_out, gate_w):

    def _A_ref(x, wq, wk, wv, wo):
        B, S, D = x.shape
        H = 32
        Dh = D // H
        q = (lambda x, *d: x.permute(*d))((x @ wq).reshape(B, S, H, Dh), 0, 2, 1, 3)
        k = x @ wk
        v = x @ wv
        scores = torch.einsum('bhqd,bkd->bhqk', q, k) * Dh ** (-0.5)
        p = _softmax(scores, axis=-1)
        o = torch.einsum('bhqk,bkd->bhqd', p, v)
        return (lambda x, *d: x.permute(*d))(o, 0, 2, 1, 3).reshape(B, S, H * Dh) @ wo

    def _B_ref(x, w_in, w_sp, b_sp, w_out):
        B, S, D = x.shape
        F = w_in.shape[-1]
        Fh = F // 2
        z = _gelu(torch.einsum('bsd,df->bsf', x, w_in))
        z1 = z[..., :Fh].clone()
        z2 = _layernorm(z[..., Fh:], axis=-1)
        g = torch.einsum('ts,bsf->btf', w_sp, z2) + b_sp[None, :, None]
        return torch.einsum('bsf,fd->bsd', z1 * g, w_out)
    x = A_x
    g = _sigmoid((x * gate_w).sum(-1, keepdims=True))
    a = _A_ref(x, A_wq, A_wk, A_wv, A_wo)
    b = _B_ref(x, B_w_in, B_w_sp, B_b_sp, B_w_out)
    return g * a + (1 - g) * b
```

```cpp
#include <cuda_runtime.h>
#include <cuda.h>
#include <cuda_bf16.h>
#include <stdint.h>

typedef __nv_bfloat16 bf16;

constexpr int S_ = 2048, D_ = 640, DH = 20, FH = 864;
constexpr int NC_Q = D_ / 8;
constexpr int NC_Z = FH / 8;
constexpr int NC_AU = (D_ + FH) / 8;

__device__ __align__(1024) bf16  g_q[S_ * D_];
__device__ __align__(1024) bf16  g_kv[S_ * 48];
__device__ __align__(1024) float g_gate[S_];
__device__ __align__(1024) bf16  g_z1[S_ * FH];
__device__ __align__(1024) bf16  g_z2[S_ * FH];
__device__ __align__(1024) bf16  g_au[S_ * (D_ + FH)];
__device__ __align__(1024) uint2 g_ln[4 * S_];
enum { F_KV = 0, F_Z = 1, F_DONE = 2, F_U = 3, F_O0 = 35, F_O1 = 67, F_Z1 = 99, F_NUM = 131 };
__device__ __align__(1024) unsigned g_flags[F_NUM * 32];

__device__ __forceinline__ uint32_t smem_u32(const void* p) { return (uint32_t)__cvta_generic_to_shared(p); }
__device__ __forceinline__ void mbar_init(uint32_t a, int c) { asm volatile("mbarrier.init.shared::cta.b64 [%0], %1;" ::"r"(a), "r"(c) : "memory"); }
__device__ __forceinline__ void mbar_expect(uint32_t a, uint32_t b) { asm volatile("mbarrier.arrive.expect_tx.shared::cta.b64 _, [%0], %1;" ::"r"(a), "r"(b) : "memory"); }
__device__ __forceinline__ void mbar_arrive(uint32_t a) { asm volatile("mbarrier.arrive.shared::cta.b64 _, [%0];" ::"r"(a) : "memory"); }
__device__ __forceinline__ void mbar_wait(uint32_t a, uint32_t ph) {
  asm volatile("{\n.reg .pred p;\n.reg .u32 n;\nmov.u32 n, 0;\n"
               "W_%=:\nmbarrier.try_wait.parity.shared::cta.b64 p, [%0], %1;\n@p bra D_%=;\n"
               "add.u32 n, n, 1;\nsetp.lt.u32 p, n, 524288;\n@p bra W_%=;\nD_%=:\n}" ::"r"(a), "r"(ph) : "memory");
}
__device__ __forceinline__ void fence_barrier_init() { asm volatile("fence.mbarrier_init.release.cluster;" ::: "memory"); }
__device__ __forceinline__ void fence_proxy_async() { asm volatile("fence.proxy.async.shared::cta;" ::: "memory"); }
__device__ __forceinline__ void tma3d(uint32_t dst, const CUtensorMap* tm, int c0, int c1, int c2, uint32_t bar) {
  asm volatile("cp.async.bulk.tensor.3d.shared::cluster.global.mbarrier::complete_tx::bytes [%0], [%1, {%3, %4, %5}], [%2];"
               ::"r"(dst), "l"(tm), "r"(bar), "r"(c0), "r"(c1), "r"(c2) : "memory");
}
__device__ __forceinline__ void tma3d_mc(uint32_t dst, const CUtensorMap* tm, int c0, int c1, int c2, uint32_t bar) {
  asm volatile("cp.async.bulk.tensor.3d.shared::cluster.global.mbarrier::complete_tx::bytes.multicast::cluster [%0], [%1, {%3, %4, %5}], [%2], %6;"
               ::"r"(dst), "l"(tm), "r"(bar), "r"(c0), "r"(c1), "r"(c2), "h"((uint16_t)3) : "memory");
}
__device__ __forceinline__ void bulk_g2s_mc(uint32_t dst, const void* src, uint32_t bytes, uint32_t bar) {
  asm volatile("cp.async.bulk.shared::cluster.global.mbarrier::complete_tx::bytes.multicast::cluster [%0], [%1], %2, [%3], %4;"
               ::"r"(dst), "l"(src), "r"(bytes), "r"(bar), "h"((uint16_t)3) : "memory");
}
__device__ __forceinline__ void mbar_arrive_pair(uint32_t a, uint32_t lane) {
  if (lane < 2)
    asm volatile("{\n.reg .b32 r;\nmapa.shared::cluster.u32 r, %0, %1;\nmbarrier.arrive.shared::cluster.b64 _, [r];\n}" ::"r"(a), "r"(lane) : "memory");
}
__device__ __forceinline__ void cluster_sync() { asm volatile("barrier.cluster.arrive.relaxed.aligned;\nbarrier.cluster.wait.aligned;" ::: "memory"); }
__device__ __forceinline__ void wg_fence() { asm volatile("wgmma.fence.sync.aligned;" ::: "memory"); }
__device__ __forceinline__ void wg_commit() { asm volatile("wgmma.commit_group.sync.aligned;" ::: "memory"); }
template <int N> __device__ __forceinline__ void wg_wait() { asm volatile("wgmma.wait_group.sync.aligned %0;" ::"n"(N) : "memory"); }
template <int N> __device__ __forceinline__ void fence_regs(float (&d)[N]) {
#pragma unroll
  for (int i = 0; i < N; i++) asm volatile("" : "+f"(d[i])::"memory");
}
template <int N> __device__ __forceinline__ void fence_regs(uint32_t (&d)[N]) {
#pragma unroll
  for (int i = 0; i < N; i++) asm volatile("" : "+r"(d[i])::"memory");
}
__device__ __forceinline__ uint64_t mk64(uint32_t lo, uint32_t hi) { uint64_t d; asm("mov.b64 %0, {%1, %2};" : "=l"(d) : "r"(lo), "r"(hi)); return d; }
__device__ __forceinline__ float ex2(float x) { float y; asm("ex2.approx.ftz.f32 %0, %1;" : "=f"(y) : "f"(x)); return y; }
__device__ __forceinline__ float rcp(float x) { float y; asm("rcp.approx.ftz.f32 %0, %1;" : "=f"(y) : "f"(x)); return y; }
__device__ __forceinline__ float sqrt_a(float x) { float y; asm("sqrt.approx.f32 %0, %1;" : "=f"(y) : "f"(x)); return y; }
__device__ __forceinline__ float rsqrt_a(float x) { float y; asm("rsqrt.approx.f32 %0, %1;" : "=f"(y) : "f"(x)); return y; }
__device__ __forceinline__ uint32_t pack2(float lo, float hi) { uint32_t y; asm("cvt.rn.bf16x2.f32 %0, %1, %2;" : "=r"(y) : "f"(hi), "f"(lo)); return y; }
__device__ __forceinline__ float bf_lo(uint32_t v) { return __uint_as_float(v << 16); }
__device__ __forceinline__ float bf_hi(uint32_t v) { return __uint_as_float(v & 0xFFFF0000u); }
__device__ __forceinline__ uint32_t hfma2(uint32_t a, uint32_t b, uint32_t c) { uint32_t y; asm("fma.rn.bf16x2 %0, %1, %2, %3;" : "=r"(y) : "r"(a), "r"(b), "r"(c)); return y; }
__device__ __forceinline__ uint32_t bsel(uint32_t a, uint32_t b) { uint32_t y; asm("lop3.b32 %0, %1, %2, 0x007F007F, 0xD8;" : "=r"(y) : "r"(a), "r"(b)); return y; }

__device__ __forceinline__ void wgmma_rs_n64_tb0(float (&d)[32], uint32_t a0, uint32_t a1, uint32_t a2, uint32_t a3, uint64_t descB, int scaleD) {
  asm volatile("{\n.reg .pred p;\nsetp.ne.b32 p, %37, 0;\n"
    "wgmma.mma_async.sync.aligned.m64n64k16.f32.bf16.bf16 {%0, %1, %2, %3, %4, %5, %6, %7, %8, %9, %10, %11, %12, %13, %14, %15, %16, %17, %18, %19, %20, %21, %22, %23, %24, %25, %26, %27, %28, %29, %30, %31}, {%32, %33, %34, %35}, %36, p, 1, 1, 0;\n}\n"
    : "+f"(d[0]), "+f"(d[1]), "+f"(d[2]), "+f"(d[3]), "+f"(d[4]), "+f"(d[5]), "+f"(d[6]), "+f"(d[7]), "+f"(d[8]), "+f"(d[9]), "+f"(d[10]), "+f"(d[11]), "+f"(d[12]), "+f"(d[13]), "+f"(d[14]), "+f"(d[15]), "+f"(d[16]), "+f"(d[17]), "+f"(d[18]), "+f"(d[19]), "+f"(d[20]), "+f"(d[21]), "+f"(d[22]), "+f"(d[23]), "+f"(d[24]), "+f"(d[25]), "+f"(d[26]), "+f"(d[27]), "+f"(d[28]), "+f"(d[29]), "+f"(d[30]), "+f"(d[31])
    : "r"(a0), "r"(a1), "r"(a2), "r"(a3), "l"(descB), "r"(scaleD));
}
__device__ __forceinline__ void wgmma_rs_n64_tb0_z(float (&d)[32], uint32_t a0, uint32_t a1, uint32_t a2, uint32_t a3, uint64_t descB) {
  asm volatile("{\n.reg .pred p;\nsetp.ne.b32 p, 0, 0;\n"
    "wgmma.mma_async.sync.aligned.m64n64k16.f32.bf16.bf16 {%0, %1, %2, %3, %4, %5, %6, %7, %8, %9, %10, %11, %12, %13, %14, %15, %16, %17, %18, %19, %20, %21, %22, %23, %24, %25, %26, %27, %28, %29, %30, %31}, {%32, %33, %34, %35}, %36, p, 1, 1, 0;\n}\n"
    : "=f"(d[0]), "=f"(d[1]), "=f"(d[2]), "=f"(d[3]), "=f"(d[4]), "=f"(d[5]), "=f"(d[6]), "=f"(d[7]), "=f"(d[8]), "=f"(d[9]), "=f"(d[10]), "=f"(d[11]), "=f"(d[12]), "=f"(d[13]), "=f"(d[14]), "=f"(d[15]), "=f"(d[16]), "=f"(d[17]), "=f"(d[18]), "=f"(d[19]), "=f"(d[20]), "=f"(d[21]), "=f"(d[22]), "=f"(d[23]), "=f"(d[24]), "=f"(d[25]), "=f"(d[26]), "=f"(d[27]), "=f"(d[28]), "=f"(d[29]), "=f"(d[30]), "=f"(d[31])
    : "r"(a0), "r"(a1), "r"(a2), "r"(a3), "l"(descB));
}
__device__ __forceinline__ void wgmma_rs_n24_tb1(float (&d)[12], uint32_t a0, uint32_t a1, uint32_t a2, uint32_t a3, uint64_t descB, int scaleD) {
  asm volatile("{\n.reg .pred p;\nsetp.ne.b32 p, %17, 0;\n"
    "wgmma.mma_async.sync.aligned.m64n24k16.f32.bf16.bf16 {%0, %1, %2, %3, %4, %5, %6, %7, %8, %9, %10, %11}, {%12, %13, %14, %15}, %16, p, 1, 1, 1;\n}\n"
    : "+f"(d[0]), "+f"(d[1]), "+f"(d[2]), "+f"(d[3]), "+f"(d[4]), "+f"(d[5]), "+f"(d[6]), "+f"(d[7]), "+f"(d[8]), "+f"(d[9]), "+f"(d[10]), "+f"(d[11])
    : "r"(a0), "r"(a1), "r"(a2), "r"(a3), "l"(descB), "r"(scaleD));
}
__device__ __forceinline__ void wgmma_ss_n24_ta0_tb1(float (&d)[12], uint64_t descA, uint64_t descB, int scaleD) {
  asm volatile("{\n.reg .pred p;\nsetp.ne.b32 p, %14, 0;\n"
    "wgmma.mma_async.sync.aligned.m64n24k16.f32.bf16.bf16 {%0, %1, %2, %3, %4, %5, %6, %7, %8, %9, %10, %11}, %12, %13, p, 1, 1, 0, 1;\n}\n"
    : "+f"(d[0]), "+f"(d[1]), "+f"(d[2]), "+f"(d[3]), "+f"(d[4]), "+f"(d[5]), "+f"(d[6]), "+f"(d[7]), "+f"(d[8]), "+f"(d[9]), "+f"(d[10]), "+f"(d[11])
    : "l"(descA), "l"(descB), "r"(scaleD));
}
__device__ __forceinline__ void wgmma_ss_n56_ta0_tb1(float (&d)[28], uint64_t descA, uint64_t descB, int scaleD) {
  asm volatile("{\n.reg .pred p;\nsetp.ne.b32 p, %30, 0;\n"
    "wgmma.mma_async.sync.aligned.m64n56k16.f32.bf16.bf16 {%0, %1, %2, %3, %4, %5, %6, %7, %8, %9, %10, %11, %12, %13, %14, %15, %16, %17, %18, %19, %20, %21, %22, %23, %24, %25, %26, %27}, %28, %29, p, 1, 1, 0, 1;\n}\n"
    : "+f"(d[0]), "+f"(d[1]), "+f"(d[2]), "+f"(d[3]), "+f"(d[4]), "+f"(d[5]), "+f"(d[6]), "+f"(d[7]), "+f"(d[8]), "+f"(d[9]), "+f"(d[10]), "+f"(d[11]), "+f"(d[12]), "+f"(d[13]), "+f"(d[14]), "+f"(d[15]), "+f"(d[16]), "+f"(d[17]), "+f"(d[18]), "+f"(d[19]), "+f"(d[20]), "+f"(d[21]), "+f"(d[22]), "+f"(d[23]), "+f"(d[24]), "+f"(d[25]), "+f"(d[26]), "+f"(d[27])
    : "l"(descA), "l"(descB), "r"(scaleD));
}
__device__ __forceinline__ void wgmma_ss_n64_ta0_tb1(float (&d)[32], uint64_t descA, uint64_t descB, int scaleD) {
  asm volatile("{\n.reg .pred p;\nsetp.ne.b32 p, %34, 0;\n"
    "wgmma.mma_async.sync.aligned.m64n64k16.f32.bf16.bf16 {%0, %1, %2, %3, %4, %5, %6, %7, %8, %9, %10, %11, %12, %13, %14, %15, %16, %17, %18, %19, %20, %21, %22, %23, %24, %25, %26, %27, %28, %29, %30, %31}, %32, %33, p, 1, 1, 0, 1;\n}\n"
    : "+f"(d[0]), "+f"(d[1]), "+f"(d[2]), "+f"(d[3]), "+f"(d[4]), "+f"(d[5]), "+f"(d[6]), "+f"(d[7]), "+f"(d[8]), "+f"(d[9]), "+f"(d[10]), "+f"(d[11]), "+f"(d[12]), "+f"(d[13]), "+f"(d[14]), "+f"(d[15]), "+f"(d[16]), "+f"(d[17]), "+f"(d[18]), "+f"(d[19]), "+f"(d[20]), "+f"(d[21]), "+f"(d[22]), "+f"(d[23]), "+f"(d[24]), "+f"(d[25]), "+f"(d[26]), "+f"(d[27]), "+f"(d[28]), "+f"(d[29]), "+f"(d[30]), "+f"(d[31])
    : "l"(descA), "l"(descB), "r"(scaleD));
}
__device__ __forceinline__ void wgmma_ss_n80_ta0_tb1(float (&d)[40], uint64_t descA, uint64_t descB, int scaleD) {
  asm volatile("{\n.reg .pred p;\nsetp.ne.b32 p, %42, 0;\n"
    "wgmma.mma_async.sync.aligned.m64n80k16.f32.bf16.bf16 {%0, %1, %2, %3, %4, %5, %6, %7, %8, %9, %10, %11, %12, %13, %14, %15, %16, %17, %18, %19, %20, %21, %22, %23, %24, %25, %26, %27, %28, %29, %30, %31, %32, %33, %34, %35, %36, %37, %38, %39}, %40, %41, p, 1, 1, 0, 1;\n}\n"
    : "+f"(d[0]), "+f"(d[1]), "+f"(d[2]), "+f"(d[3]), "+f"(d[4]), "+f"(d[5]), "+f"(d[6]), "+f"(d[7]), "+f"(d[8]), "+f"(d[9]), "+f"(d[10]), "+f"(d[11]), "+f"(d[12]), "+f"(d[13]), "+f"(d[14]), "+f"(d[15]), "+f"(d[16]), "+f"(d[17]), "+f"(d[18]), "+f"(d[19]), "+f"(d[20]), "+f"(d[21]), "+f"(d[22]), "+f"(d[23]), "+f"(d[24]), "+f"(d[25]), "+f"(d[26]), "+f"(d[27]), "+f"(d[28]), "+f"(d[29]), "+f"(d[30]), "+f"(d[31]), "+f"(d[32]), "+f"(d[33]), "+f"(d[34]), "+f"(d[35]), "+f"(d[36]), "+f"(d[37]), "+f"(d[38]), "+f"(d[39])
    : "l"(descA), "l"(descB), "r"(scaleD));
}
__device__ __forceinline__ void wgmma_ss_n96_ta0_tb1(float (&d)[48], uint64_t descA, uint64_t descB, int scaleD) {
  asm volatile("{\n.reg .pred p;\nsetp.ne.b32 p, %50, 0;\n"
    "wgmma.mma_async.sync.aligned.m64n96k16.f32.bf16.bf16 {%0, %1, %2, %3, %4, %5, %6, %7, %8, %9, %10, %11, %12, %13, %14, %15, %16, %17, %18, %19, %20, %21, %22, %23, %24, %25, %26, %27, %28, %29, %30, %31, %32, %33, %34, %35, %36, %37, %38, %39, %40, %41, %42, %43, %44, %45, %46, %47}, %48, %49, p, 1, 1, 0, 1;\n}\n"
    : "+f"(d[0]), "+f"(d[1]), "+f"(d[2]), "+f"(d[3]), "+f"(d[4]), "+f"(d[5]), "+f"(d[6]), "+f"(d[7]), "+f"(d[8]), "+f"(d[9]), "+f"(d[10]), "+f"(d[11]), "+f"(d[12]), "+f"(d[13]), "+f"(d[14]), "+f"(d[15]), "+f"(d[16]), "+f"(d[17]), "+f"(d[18]), "+f"(d[19]), "+f"(d[20]), "+f"(d[21]), "+f"(d[22]), "+f"(d[23]), "+f"(d[24]), "+f"(d[25]), "+f"(d[26]), "+f"(d[27]), "+f"(d[28]), "+f"(d[29]), "+f"(d[30]), "+f"(d[31]), "+f"(d[32]), "+f"(d[33]), "+f"(d[34]), "+f"(d[35]), "+f"(d[36]), "+f"(d[37]), "+f"(d[38]), "+f"(d[39]), "+f"(d[40]), "+f"(d[41]), "+f"(d[42]), "+f"(d[43]), "+f"(d[44]), "+f"(d[45]), "+f"(d[46]), "+f"(d[47])
    : "l"(descA), "l"(descB), "r"(scaleD));
}


template <int BN> struct WG;
#define DEF_WG(N) template <> struct WG<N> { static __device__ __forceinline__ void mma(float (&d)[N / 2], uint64_t a, uint64_t b, int s) { wgmma_ss_n##N##_ta0_tb1(d, a, b, s); } };
DEF_WG(24) DEF_WG(56) DEF_WG(64) DEF_WG(80) DEF_WG(96)
template <int N1, int N2, int N3> struct Acc {
  float a[N1 / 2], b[N2 / 2], c[N3 ? N3 / 2 : 1];
  __device__ __forceinline__ float& operator[](int i) { return i < N1 / 2 ? a[i] : (i < (N1 + N2) / 2 ? b[i - N1 / 2] : c[i - (N1 + N2) / 2]); }
  __device__ __forceinline__ void zero() {
#pragma unroll
    for (int i = 0; i < (N1 + N2 + N3) / 2; i++) (*this)[i] = 0.f;
  }
  __device__ __forceinline__ void fence() { fence_regs(a); fence_regs(b); if (N3) fence_regs(c); }
};

__device__ __forceinline__ void bar_sync(int id, int n) { asm volatile("bar.sync %0, %1;" ::"r"(id), "r"(n) : "memory"); }
__device__ __forceinline__ void fence_proxy_all() { asm volatile("fence.proxy.async;" ::: "memory"); }
__device__ __forceinline__ void flag_post(int flag) {
  fence_proxy_all();
  asm volatile("red.relaxed.gpu.global.add.u32 [%0], 1;" ::"l"(g_flags + flag * 32) : "memory");
}
__device__ __forceinline__ unsigned flag_read(int flag) {
  unsigned v;
  asm volatile("ld.acquire.gpu.global.u32 %0, [%1];" : "=r"(v) : "l"(g_flags + flag * 32) : "memory");
  return v;
}
__device__ __forceinline__ void flag_wait(int flag, unsigned target, unsigned ns) {
#pragma unroll 1
  for (int n = 0; n < (1 << 20) && flag_read(flag) < target; n++) __nanosleep(ns);
  asm volatile("fence.proxy.async.global;" ::: "memory");
}

__host__ __device__ constexpr bool is_poly_blk(int b) { return b >= 2; }
constexpr float QSCALE = 1.4426950408889634f * 0.22360679774997896f;

__device__ __forceinline__ int tile160_c0(int nt) { return (nt >> 1) * 320 + (nt & 1) * 192; }
__device__ __forceinline__ int tile160_ch(int nt) { return (nt >> 1) * 320 + 128 + (nt & 1) * 32; }
__device__ __forceinline__ int ztile_c0(int T) { return T < 4 ? (T == 0 ? 0 : 64 + 192 * T) : (T < 6 ? 896 + 192 * (T - 4) : 960 + 192 * (T - 4)); }
__device__ __forceinline__ int ztile_ch(int T) { return T < 2 ? 192 + 32 * T : (T < 5 ? (T == 4 ? 864 : 832) : 1280 + 32 * (T - 5)); }

__device__ __forceinline__ float gelu_tanh(float x) {
  const float u = x * fmaf(x * x, 0.7978845608028654f * 0.044715f, 0.7978845608028654f);
  float th;
  asm("tanh.approx.f32 %0, %1;" : "=f"(th) : "f"(u));
  const float hx = 0.5f * x;
  return fmaf(hx, th, hx);
}
__device__ __forceinline__ float nanmax(float a, float b) { return (b > a || b != b) ? b : a; }

constexpr int G_ST = 5, G_STAGE = 36864;
constexpr int H_WQ = 8192, H_HALF = 24576;
constexpr int AT_ST = 3, AT_STAGE = 12288;
constexpr int Z1_SPLIT = 5;
constexpr int HOLD = 5;
constexpr int OFF_AT = G_ST * G_STAGE, OFF_KVW = OFF_AT;
constexpr int OFF_BAR = OFF_AT + AT_ST * AT_STAGE;
constexpr int B_GFULL = 0, B_GEMPTY = 8 * G_ST, B_HFULL = 16 * G_ST, B_HEMPTY = 24 * G_ST, B_AFULL = 32 * G_ST, B_AEMPTY = B_AFULL + 8 * AT_ST,
              B_EV = B_AEMPTY + 8 * AT_ST;
enum { E_Q = 0, E_S0D, E_Z, E_Z1, E_O0, E_O1, E_U, E_GO, E_LNOK, E_BC, E_NUM };
constexpr int NBAR = B_EV / 8 + E_NUM;
enum { SL_S0 = 0, IT_SP = 3, IT_Z1 = 35, IT_O0 = 36, IT_U = 41, IT_O1 = 55, IT_END = 60 };
constexpr int OFF_BC = OFF_BAR + 384;
constexpr int OFF_LN = OFF_BC + 128;
constexpr int OFF_HS = OFF_LN + 3072;
constexpr int SMEM_BYTES = OFF_HS + 4096;
static_assert(NBAR * 8 <= 384 && NBAR <= 64 && SMEM_BYTES <= 232448, "smem map");

__host__ __device__ constexpr int bar_count(int i) {
  return i < G_ST ? 2 : (i < 2 * G_ST ? 8 : (i < 3 * G_ST ? 3 : (i < 4 * G_ST ? 32 : (i < 4 * G_ST + AT_ST ? 1 : (i < B_EV / 8 ? 32 :
         (i - B_EV / 8 == E_S0D ? 8 : i - B_EV / 8 == E_U || i - B_EV / 8 == E_Z1 || i - B_EV / 8 == E_Z ? 4 :
         (i - B_EV / 8 == E_GO || i - B_EV / 8 == E_LNOK || i - B_EV / 8 == E_BC ? 1 : 16)))))));
}
__host__ __device__ constexpr unsigned long long bar_pack(int q) {
  unsigned long long v = 0;
  for (int i = 0; i < 8; i++) v |= (unsigned long long)bar_count(8 * q + i) << (8 * i);
  return v;
}
__constant__ unsigned long long BAR_CNT[6] = {bar_pack(0), bar_pack(1), bar_pack(2), bar_pack(3), bar_pack(4), bar_pack(5)};

struct Maps {
  CUtensorMap x, wq, wqh, win, winh, wsp, z1, z2, au, wo, woh, wout, wouth;
  const void* pf_ptr[6];
  uint32_t pf_chunk[6];
  uint32_t m16;
};
__device__ __forceinline__ void l2_prefetch(const void* p, uint32_t bytes) {
  asm volatile("cp.async.bulk.prefetch.L2.global [%0], %1;" ::"l"(p), "r"(bytes) : "memory");
}
__device__ __forceinline__ void pf_issue(const Maps& m, int i0, int i1) {
#pragma unroll 1
  for (int i = i0; i < i1; i++) {
    const uint32_t n = m.pf_chunk[i];
    const unsigned char* q = (const unsigned char*)m.pf_ptr[i] + (size_t)blockIdx.x * n;
#pragma unroll 1
    for (uint32_t o = 0; o < n; o += 32768) l2_prefetch(q + o, n - o < 32768 ? n - o : 32768);
  }
}
__device__ __forceinline__ int cta_mb() { return (blockIdx.x >> 3) * 2 + (blockIdx.x & 1); }
__device__ __forceinline__ int cta_j() { return (blockIdx.x >> 1) & 3; }
__device__ __forceinline__ void ev_arrive(uint32_t sb, int e) {
  __syncwarp();
  if ((threadIdx.x & 31) == 0) mbar_arrive(sb + OFF_BAR + B_EV + 8 * e);
}

__device__ __forceinline__ bool elect_one() {
  uint32_t ok;
  asm volatile("{\n.reg .pred p;\nelect.sync _|p, 0xffffffff;\nselp.u32 %0, 1, 0, p;\n}" : "=r"(ok));
  return ok != 0;
}
struct Prod {
  uint32_t sb, s, ph;
  uint32_t lo;
  uint32_t eb;
  template <int NST> __device__ __forceinline__ void next() { if (++s == NST) { s = lo; ph ^= 1; } }
};
template <bool MC, bool TWO>
__device__ __forceinline__ void prod_run(Prod& p, int n, uint32_t bytes, const CUtensorMap* m1, int c1, int d1, int c2, int d2, uint32_t off1,
                                         const CUtensorMap* m2 = nullptr, int c2b = 0, uint32_t off2 = 0) {
#pragma unroll 1
  for (int i = 0; i < n; i++) {
    const uint32_t bar = p.sb + OFF_BAR + 8 * p.s, dst = p.sb + p.s * G_STAGE;
    mbar_wait(bar + p.eb, p.ph);
    if (elect_one()) {
      mbar_expect(bar + B_GFULL, bytes);
      if (MC) tma3d_mc(dst + off1, m1, 0, c1, c2, bar + B_GFULL); else tma3d(dst + off1, m1, 0, c1, c2, bar + B_GFULL);
      if (TWO) tma3d_mc(dst + off2, m2, 0, c1, c2b, bar + B_GFULL);
    }
    c1 += d1; c2 += d2;
    p.next<G_ST>();
  }
}
__device__ __forceinline__ void prod_skip(Prod& p) {
  const uint32_t bar = p.sb + OFF_BAR + 8 * p.s;
  mbar_wait(bar + B_GEMPTY, p.ph);
  if (elect_one()) mbar_arrive(bar + B_GFULL);
  p.next<G_ST>();
}
__device__ __forceinline__ void warp_flag_wait(int flag, unsigned target, unsigned ns) {
  if (elect_one()) flag_wait(flag, target, ns);
  __syncwarp();
}

__device__ __forceinline__ void service_role(const Maps& m, uint32_t sb, unsigned char* sm) {
  const int w = __shfl_sync(0xffffffffu, (int)((threadIdx.x >> 5) & 3), 0);
  const int mb = cta_mb(), j = cta_j(), r = blockIdx.x & 1;
  const uint32_t bb = sb + OFF_BAR;
  if (w < 3) {
    const CUtensorMap* m1 = w == 1 ? &m.wq : &m.winh;
    const CUtensorMap* m2 = w == 0 ? &m.wqh : &m.winh;
    const int c2a = w == 1 ? tile160_c0(j) >> 6 : ztile_ch(4 + j) >> 5;
    const int c2b = (w == 0 ? tile160_ch(j) : ztile_ch(j)) >> 5;
    const uint32_t off1 = w == 1 ? H_WQ + r * 8192 : H_HALF + r * 6144 + 2048, off2 = H_HALF + r * 6144 + w * 2048;
    const bool on = w < 2 || j != 3;
    const uint32_t bytes = w == 0 ? 12288 : (w == 1 ? 16384 : (on ? 8192 : 0));
    uint32_t s = 0;
#pragma unroll 1
    for (int it = 0; it < 10; it++) {
      const uint32_t dst = sb + s * G_STAGE, fb = bb + B_HFULL + 8 * s;
      if (it >= G_ST) mbar_wait(bb + B_HEMPTY + 8 * s, 0);
      if (elect_one()) {
        mbar_expect(fb, bytes);
        if (w == 0) tma3d(dst, &m.x, 0, mb * 64, it, fb); else if (on) tma3d_mc(dst + off1, m1, 0, it * 64 + r * 32, c2a, fb);
        if (w != 1 && on) tma3d_mc(dst + off2, m2, 0, it * 64 + r * 32, c2b, fb);
      }
      if (++s == G_ST) s = 0;
    }
  }
  if (w < 2) {
    Prod p; p.sb = sb; p.s = 0; p.ph = 1; p.lo = 0; p.eb = B_HEMPTY;
#pragma unroll 1
    for (int q = 0; q < 3; q++) {
      const int kb = q == 1 ? 5 : 0, n = q == 2 ? 10 : 5;
      if (w == 0) prod_run<false, false>(p, n, 8192, &m.x, mb * 64, 0, kb, 1, 0);
      else prod_run<true, false>(p, n, 24576, &m.win, kb * 64 + r * 32, 64, ztile_c0(q == 2 ? j : 4 + j) >> 6, 0, 8192 + r * 12288);
      p.eb = B_GEMPTY;
      if (q == 1) prod_skip(p);
      p.lo = q == 1 ? 1 : 0;
    }
    if (w == 0) {
      prod_run<false, false>(p, 32, 8192, &m.wsp, mb * 64, 0, 0, 1, 0);
      prod_skip(p);
#pragma unroll 1
      for (int q = 0; q < 3; q++) {
        if (q == 1) { mbar_wait(bb + B_EV + 8 * E_U, 0); if (elect_one()) flag_post(F_U + mb); __syncwarp(); }
        if (q != 1) mbar_wait(bb + B_EV + 8 * (q == 0 ? E_O0 : E_O1), 0);
        warp_flag_wait((q == 0 ? F_O0 : (q == 1 ? F_U : F_O1)) + mb, 4, 20);
        prod_run<false, false>(p, q == 1 ? 14 : 5, 8192, &m.au, q == 0 ? 0 : (q == 1 ? 80 : 40), 8, mb * 8, 0, 0);
      }
      const int ln = threadIdx.x & 31;
      g_ln[(mb * 64 + ln) * 4 + j] = make_uint2(0u, 0u);
      g_ln[(mb * 64 + 32 + ln) * 4 + j] = make_uint2(0u, 0u);
      unsigned n = 0;
      if (ln == 0) n = atomicAdd(g_flags + F_DONE * 32, 1u);
      n = __shfl_sync(0xffffffffu, n, 0);
      if (n == gridDim.x - 1) {
#pragma unroll 1
        for (int i = ln; i < F_NUM; i += 32) *(uint4*)(g_flags + i * 32) = make_uint4(0u, 0u, 0u, 0u);
      }
    } else {
      mbar_wait(bb + B_EV + 8 * E_Z, 0);
      warp_flag_wait(F_Z, 128, 100);
      prod_run<true, false>(p, 32, 27648, &m.z2, j * 27, 0, r * 4, 8, 8192 + r * 13824);
      warp_flag_wait(F_Z1 + mb, 4, 50);
      prod_run<false, false>(p, 1, 27648, &m.z1, j * 27, 0, mb * 8, 0, 8192);
#pragma unroll 1
      for (int q = 0; q < 3; q++)
        prod_run<true, true>(p, q == 1 ? 14 : 5, 24576, q == 1 ? &m.wout : &m.wo, (q == 2 ? 320 : 0) + r * 32, 64, tile160_c0(j) >> 6, 0,
                             8192 + r * 12288, q == 1 ? &m.wouth : &m.woh, tile160_ch(j) >> 5, 16384 + r * 12288);
    }
  } else if (w == 2) {
#pragma unroll 1
    for (int e = E_Q; e <= E_O1; e++) {
      mbar_wait(bb + B_EV + 8 * e, 0);
      if (elect_one()) {
        if (e != E_S0D) flag_post(e == E_Q ? F_KV : (e == E_Z ? F_Z : (e == E_Z1 ? F_Z1 + mb : (e == E_O0 ? F_O0 + mb : F_O1 + mb))));
      }
      __syncwarp();
      if (e == E_S0D) {
        const int ln = threadIdx.x & 31;
        float2* ls = (float2*)(sm + OFF_LN);
#pragma unroll 1
        for (int h = 0; h < 2; h++) {
          const int row = h * 32 + ln;
          const float2 a = ls[row], b = ls[64 + row];
          const uint32_t lo = ~__float_as_uint(a.x + b.x), hi = ~__float_as_uint(fabsf(a.y + b.y));
          asm volatile("st.relaxed.gpu.global.v2.u32 [%0], {%1, %2};" ::"l"(g_ln + (mb * 64 + row) * 4 + j), "r"(lo), "r"(hi) : "memory");
        }
#pragma unroll 1
        for (int h = 0; h < 2; h++) {
          const int row = h * 32 + ln;
          const uint2* p = g_ln + (mb * 64 + row) * 4;
          unsigned long long v0, v1, v2, v3;
#pragma unroll 1
          for (int n = 0; n < (1 << 20); n++) {
            asm volatile("ld.relaxed.gpu.global.v2.u64 {%0, %1}, [%2];" : "=l"(v0), "=l"(v1) : "l"(p) : "memory");
            asm volatile("ld.relaxed.gpu.global.v2.u64 {%0, %1}, [%2];" : "=l"(v2), "=l"(v3) : "l"(p + 2) : "memory");
            if (__all_sync(0xffffffffu, (v0 & v1 & v2 & v3) >> 63)) break;
            __nanosleep(40);
          }
          const float sm_ = (__uint_as_float(~(uint32_t)v0) + __uint_as_float(~(uint32_t)v1)) + (__uint_as_float(~(uint32_t)v2) + __uint_as_float(~(uint32_t)v3));
          const float sq = (__uint_as_float(~(uint32_t)(v0 >> 32)) + __uint_as_float(~(uint32_t)(v1 >> 32))) +
                           (__uint_as_float(~(uint32_t)(v2 >> 32)) + __uint_as_float(~(uint32_t)(v3 >> 32)));
          const float mean = sm_ * (1.f / FH);
          const float rs = rsqrt_a(fmaxf(sq * (1.f / FH) - mean * mean, 0.f) + 1e-5f);
          ls[320 + row] = make_float2(rs, -mean * rs);
        }
        __syncwarp();
        if (elect_one()) { mbar_arrive(bb + B_EV + 8 * E_LNOK); }
      }
    }
  } else {
    if (elect_one()) pf_issue(m, 0, 3);
    mbar_wait(bb + B_EV + 8 * E_Q, 0);
    if (elect_one()) {
      uint32_t cnt, kmax, vmax, pad;
#pragma unroll 1
      for (int n = 0; n < (1 << 20); n++) {
        asm volatile("ld.acquire.gpu.global.v4.u32 {%0, %1, %2, %3}, [%4];" : "=r"(cnt), "=r"(kmax), "=r"(vmax), "=r"(pad) : "l"(g_flags + F_KV * 32) : "memory");
        if (cnt >= 128) break;
        __nanosleep(100);
      }
      asm volatile("fence.proxy.async.global;" ::: "memory");
      asm volatile("st.shared.v4.u32 [%0], {%1, %2, %3, %3};" ::"r"(sb + OFF_BC), "r"(kmax), "r"(vmax), "r"(pad) : "memory");
      mbar_arrive(bb + B_EV + 8 * E_GO);
    }
    __syncwarp();
    const int ln = threadIdx.x & 31;
    const float gt = __ldcg(g_gate + (mb * 4 + j) * 16 + (ln & 15));
    const uint32_t h = r * (AT_STAGE / 2);
    uint32_t s = 0, ph = 1;
#pragma unroll 1
    for (int it = 0; it < 32; it++) {
      mbar_wait(bb + B_AEMPTY + 8 * s, ph);
      if (elect_one()) {
        mbar_expect(bb + B_AFULL + 8 * s, AT_STAGE);
        bulk_g2s_mc(sb + OFF_AT + s * AT_STAGE + h, (const unsigned char*)g_kv + (size_t)(it & 15) * AT_STAGE + h, AT_STAGE / 2, bb + B_AFULL + 8 * s);
      }
      __syncwarp();
      if (it == AT_ST - 1) {
        if (ln < 16) asm volatile("st.shared.f32 [%0], %1;" ::"r"(sb + OFF_BC + 16 + 4 * ln), "f"(gt) : "memory");
        __syncwarp();
        if (elect_one()) mbar_arrive(bb + B_EV + 8 * E_BC);
      }
      if (it >= AT_ST && it < AT_ST + 6 && elect_one()) {
        if (it < AT_ST + 4) l2_prefetch((const unsigned char*)m.pf_ptr[3] + (size_t)blockIdx.x * 65536 + (it - AT_ST) * 16384, 16384);
        else pf_issue(m, it - AT_ST, it - AT_ST + 1);
      }
      if (++s == AT_ST) { s = 0; ph ^= 1; }
    }
  }
}

struct DSwzA { static constexpr uint32_t LO = 1u << 16, HI = 64u | (1u << 30), PLO = 1u << 16, PHI = 0; static __host__ __device__ constexpr int koff(int k) { return 2 * k; } };
struct DCmA  { static constexpr uint32_t LO = 8u << 16, HI = 64u, PLO = 0, PHI = 1u << 17; static __host__ __device__ constexpr int koff(int k) { return 16 * k; } };
template <int NSLOT> struct DSwzB {
  static constexpr uint32_t LO = 256u << 16, HI = 64u | (1u << 30), NOFF8 = 32;
  static __host__ __device__ constexpr int koff(int k) { return (k >> 1) * NSLOT * 256 + (k & 1) * 128; }
};
struct DCmB  { static constexpr uint32_t LO = 216u << 16, HI = 8u, NOFF8 = 8; static __host__ __device__ constexpr int koff(int k) { return 432 * k; } };

template <class DA, class DB, int GRAN, int N1, int N2, int N3>
__device__ __forceinline__ void gemm_run(Acc<N1, N2, N3>& acc, uint32_t sb, int it0, int nkb, int nst, uint32_t stage16, uint32_t boff16,
                                         uint32_t full, uint32_t empty, bool first = true) {
  const uint32_t lane = threadIdx.x & 31;
  const uint32_t sb4 = (sb & 0x3FFFFu) >> 4;
  int s = it0 % nst, ph = (it0 / nst) & 1, ps = 0;
  acc.fence();
#pragma unroll 1
  for (int kb = 0; kb < nkb; kb++) {
    mbar_wait(full + 8 * s, ph);
    const uint32_t sa = sb4 + s * stage16;
    const int sc = (kb > 0 || !first) ? 1 : 0;
    const uint64_t da = mk64(sa | DA::LO, DA::HI), da2 = DA::PHI ? mk64(sa | DA::LO, DA::HI | DA::PHI) : da + DA::PLO;
    const uint64_t db = mk64((sa + boff16) | DB::LO, DB::HI);
    wg_fence();
#pragma unroll
    for (int k = 0; k < 4; k++) {
      WG<N1>::mma(acc.a, da + DA::koff(k), db + DB::koff(k), k > 0 ? 1 : sc);
      WG<N2>::mma(acc.b, da2 + DA::koff(k), db + DB::koff(k) + (N1 / 8) * DB::NOFF8, k > 0 ? 1 : sc);
      if constexpr (N3 > 0) {
        WG<N3>::mma(acc.c, da + 2 * DA::PLO + DA::koff(k), db + DB::koff(k) + ((N1 + N2) / 8) * DB::NOFF8, k > 0 ? 1 : sc);
      }
      if (GRAN == 1) { wg_commit(); wg_wait<1>(); }
      if (GRAN == 1 && k == 0 && kb > 0) mbar_arrive_pair(empty + 8 * ps, lane);
    }
    if (GRAN == 0) {
      wg_commit();
      wg_wait<1>();
      if (kb > 0) mbar_arrive_pair(empty + 8 * ps, lane);
    }
    ps = s;
    if (++s == nst) { s = 0; ph ^= 1; }
  }
  wg_wait<0>();
  acc.fence();
  mbar_arrive_pair(empty + 8 * ps, lane);
}

__device__ __forceinline__ uint4 gelu8(float x0, float x1, float x2, float x3, float x4, float x5, float x6, float x7, float (&st)[4]) {
  const float y0 = gelu_tanh(x0), y1 = gelu_tanh(x1), y2 = gelu_tanh(x2), y3 = gelu_tanh(x3);
  const float y4 = gelu_tanh(x4), y5 = gelu_tanh(x5), y6 = gelu_tanh(x6), y7 = gelu_tanh(x7);
  st[0] += (y0 + y1) + (y4 + y5); st[1] += (y2 + y3) + (y6 + y7);
  st[2] = fmaf(y0, y0, fmaf(y1, y1, fmaf(y4, y4, fmaf(y5, y5, st[2]))));
  st[3] = fmaf(y2, y2, fmaf(y3, y3, fmaf(y6, y6, fmaf(y7, y7, st[3]))));
  return make_uint4(pack2(y0, y1), pack2(y2, y3), pack2(y4, y5), pack2(y6, y7));
}
__device__ __forceinline__ void ln_partial(unsigned char* sm, int set, float (&st)[4], int td) {
#pragma unroll
  for (int i = 0; i < 4; i++) { st[i] += __shfl_xor_sync(0xffffffffu, st[i], 1); st[i] += __shfl_xor_sync(0xffffffffu, st[i], 2); }
  const int t = td & 3;
  if (t < 2) ((float2*)(sm + OFF_LN))[set * 64 + ((td >> 5) & 3) * 16 + ((td & 31) >> 2) + 8 * t] = t ? make_float2(st[1], st[3]) : make_float2(st[0], st[2]);
}
__device__ __forceinline__ void gemm_role(uint32_t sb, unsigned char* sm, const bf16* __restrict__ b_sp, bf16* __restrict__ out) {
  const int gt = threadIdx.x - 512, w = gt >> 5, lane = gt & 31, g = lane >> 2, t = lane & 3;
  const int mb = cta_mb(), j = cta_j();
  const int row0 = mb * 64 + w * 16 + g;
  const int rg = mb * 8 + w * 2;
  const uint32_t bb = sb + OFF_BAR;

  {
    Acc<64, 64, 64> acc;
    acc.zero();
#pragma unroll 1
    for (int q = 0; q < 3; q++) {
      const int tl = q ? 1 : 0;
      gemm_run<DSwzA, DSwzB<3>, 1>(acc, sb + tl * G_STAGE, q == 2 ? Z1_SPLIT : 0, q == 0 ? 10 : (q == 1 ? Z1_SPLIT : 10 - Z1_SPLIT), G_ST - tl,
                                       G_STAGE / 16, 512, bb + B_GFULL + 8 * tl, bb + B_GEMPTY + 8 * tl, q != 2);
      if (q == 0) {
        uint4* scr = (uint4*)(sm + SL_S0 * G_STAGE) + gt;
        mbar_wait(bb + B_GFULL + 8 * SL_S0, 0);
#pragma unroll
        for (int i = 0; i < 12; i++)
          scr[i * 128] = make_uint4(pack2(acc[8 * i], acc[8 * i + 1]), pack2(acc[8 * i + 2], acc[8 * i + 3]),
                                    pack2(acc[8 * i + 4], acc[8 * i + 5]), pack2(acc[8 * i + 6], acc[8 * i + 7]));
        float st[4] = {0.f, 0.f, 0.f, 0.f};
#pragma unroll 2
        for (int i = 0; i < 12; i++) {
          const uint4 v = scr[i * 128];
          scr[i * 128] = gelu8(bf_lo(v.x), bf_hi(v.x), bf_lo(v.y), bf_hi(v.y), bf_lo(v.z), bf_hi(v.z), bf_lo(v.w), bf_hi(v.w), st);
        }
        ln_partial(sm, 0, st, gt);
        ev_arrive(sb, E_S0D);
      } else if (q == 2) {
        uint32_t* z1p = (uint32_t*)g_z1 + ((size_t)rg * NC_Z + (ztile_c0(j) >> 3)) * 32 + lane;
#pragma unroll
        for (int b = 0; b < 24; b++) {
          z1p[b * 32] = pack2(acc[4 * b], acc[4 * b + 1]);
          z1p[b * 32 + NC_Z * 32] = pack2(acc[4 * b + 2], acc[4 * b + 3]);
        }
        ev_arrive(sb, E_Z1);
      } else {
        mbar_wait(bb + B_EV + 8 * E_LNOK, 0);
        const float2* ls = (const float2*)(sm + OFF_LN);
        const float2 n0 = ls[320 + w * 16 + g], n1 = ls[320 + w * 16 + g + 8];
        const uint4* scr = (const uint4*)(sm + SL_S0 * G_STAGE) + gt;
        uint32_t* z2b = (uint32_t*)g_z2 + ((size_t)rg * NC_Z - NC_Z) * 32 + lane;
        uint32_t* p = z2b + (ztile_c0(4 + j) >> 3) * 32;
        const int np = j != 3 ? 7 : 6;
#pragma unroll 1
        for (int i = 0; i < np; i++) {
          if (i == 6) { scr = (const uint4*)(sm + OFF_HS) + gt; p = z2b + (ztile_ch(4 + j) >> 3) * 32; }
          const uint4 v = scr[0], u = scr[128];
          p[0] = pack2(fmaf(bf_lo(v.x), n0.x, n0.y), fmaf(bf_hi(v.x), n0.x, n0.y));
          p[NC_Z * 32] = pack2(fmaf(bf_lo(v.y), n1.x, n1.y), fmaf(bf_hi(v.y), n1.x, n1.y));
          p[32] = pack2(fmaf(bf_lo(v.z), n0.x, n0.y), fmaf(bf_hi(v.z), n0.x, n0.y));
          p[NC_Z * 32 + 32] = pack2(fmaf(bf_lo(v.w), n1.x, n1.y), fmaf(bf_hi(v.w), n1.x, n1.y));
          p[64] = pack2(fmaf(bf_lo(u.x), n0.x, n0.y), fmaf(bf_hi(u.x), n0.x, n0.y));
          p[NC_Z * 32 + 64] = pack2(fmaf(bf_lo(u.y), n1.x, n1.y), fmaf(bf_hi(u.y), n1.x, n1.y));
          p[96] = pack2(fmaf(bf_lo(u.z), n0.x, n0.y), fmaf(bf_hi(u.z), n0.x, n0.y));
          p[NC_Z * 32 + 96] = pack2(fmaf(bf_lo(u.w), n1.x, n1.y), fmaf(bf_hi(u.w), n1.x, n1.y));
          scr += 256; p += 128;
        }
        fence_proxy_async();
        ev_arrive(sb, E_Z);
        mbar_arrive_pair(bb + B_GEMPTY + 8 * SL_S0, lane);
      }
    }
  }

  {
    Acc<80, 80, 56> acc;
    acc.zero();
    gemm_run<DSwzA, DCmB, 1>(acc, sb, IT_SP, 32, G_ST, G_STAGE / 16, 512, bb + B_GFULL, bb + B_GEMPTY);
    mbar_wait(bb + B_EV + 8 * E_GO, 0);
    const float f0 = 1.f - __ldcg(g_gate + row0), f1 = 1.f - __ldcg(g_gate + row0 + 8);
    const float b0 = __bfloat162float(b_sp[row0]) * f0, b1 = __bfloat162float(b_sp[row0 + 8]) * f1;
    mbar_wait(bb + B_GFULL + 8 * (IT_Z1 % G_ST), (IT_Z1 / G_ST) & 1);
    const uint32_t* zs = (const uint32_t*)(sm + (IT_Z1 % G_ST) * G_STAGE + 8192) + (w * 2) * 27 * 32 + lane;
    uint32_t* u0 = (uint32_t*)g_au + ((size_t)rg * NC_AU + 80 + j * 27) * 32 + lane;
#pragma unroll
    for (int b = 0; b < 27; b++) {
      const uint32_t za = zs[b * 32], zb = zs[(27 + b) * 32];
      u0[b * 32] = pack2(fmaf(acc[4 * b], f0, b0) * gelu_tanh(bf_lo(za)), fmaf(acc[4 * b + 1], f0, b0) * gelu_tanh(bf_hi(za)));
      u0[b * 32 + NC_AU * 32] = pack2(fmaf(acc[4 * b + 2], f1, b1) * gelu_tanh(bf_lo(zb)), fmaf(acc[4 * b + 3], f1, b1) * gelu_tanh(bf_hi(zb)));
    }
    fence_proxy_async();
    ev_arrive(sb, E_U);
    mbar_arrive_pair(bb + B_GEMPTY + 8 * (IT_Z1 % G_ST), lane);
  }

  {
    Acc<64, 96, 0> acc;
    acc.zero();
    gemm_run<DCmA, DSwzB<3>, 1>(acc, sb, IT_O0, IT_O1 - HOLD - IT_O0, G_ST, G_STAGE / 16, 512, bb + B_GFULL, bb + B_GEMPTY, true);
    mbar_wait(bb + B_EV + 8 * E_O1, 0);
    gemm_run<DCmA, DSwzB<3>, 0>(acc, sb, IT_O1 - HOLD, IT_END - IT_O1 + HOLD, G_ST, G_STAGE / 16, 512, bb + B_GFULL, bb + B_GEMPTY, false);
    asm volatile("barrier.cluster.arrive.relaxed.aligned;" ::: "memory");
    bar_sync(5, 128);
    uint32_t* st = (uint32_t*)(sm + w * 16 * 336);
#pragma unroll
    for (int b = 0; b < 20; b++) {
      st[g * 84 + b * 4 + t] = pack2(acc[4 * b], acc[4 * b + 1]);
      st[(g + 8) * 84 + b * 4 + t] = pack2(acc[4 * b + 2], acc[4 * b + 3]);
    }
    __syncwarp();
    const int c0 = tile160_c0(j), ch = tile160_ch(j);
    {
      const uint32_t* sp = st + (lane >> 4) * 84 + (lane & 15) * 4;
      bf16* op = out + (size_t)(mb * 64 + w * 16 + (lane >> 4)) * D_ + c0 + (lane & 15) * 8;
#pragma unroll
      for (int i = 0; i < 8; i++) *(uint4*)(op + (size_t)i * 2 * D_) = *(const uint4*)(sp + i * 168);
      const uint32_t* sh = st + (lane >> 2) * 84 + 64 + (lane & 3) * 4;
      bf16* oh = out + (size_t)(mb * 64 + w * 16 + (lane >> 2)) * D_ + ch + (lane & 3) * 8;
#pragma unroll
      for (int i = 0; i < 2; i++) *(uint4*)(oh + (size_t)i * 8 * D_) = *(const uint4*)(sh + i * 672);
    }
  }
}

__device__ __forceinline__ uint32_t exp2_pair(float t0, float t1, uint32_t m16) {
  const uint32_t v = __float_as_uint(t1) * m16 + __float_as_uint(t0);
  const uint32_t gh = bsel(0x3F003F00u, v);
  const uint32_t e = bsel(v, 0x00010001u);
  return hfma2(gh, v, e);
}
template <bool FAST>
__device__ __forceinline__ void att_tile(const uint32_t (&q)[8], float (&o)[12], float (&mx)[2], uint64_t kd, uint64_t vd, uint32_t m16) {
  float s[32];
  uint32_t p[16];
  wg_fence();
  wgmma_rs_n64_tb0_z(s, q[0], q[1], q[2], q[3], kd);
  wgmma_rs_n64_tb0(s, q[4], q[5], q[6], q[7], kd + 16, 1);
  wg_commit();
  wg_wait<0>(); fence_regs(s);
  if (FAST) {
#pragma unroll
    for (int b = 0; b < 8; b++) {
      if (is_poly_blk(b)) {
        p[2 * b] = exp2_pair(s[4 * b], s[4 * b + 1], m16);
        p[2 * b + 1] = exp2_pair(s[4 * b + 2], s[4 * b + 3], m16);
      } else {
        p[2 * b] = pack2(ex2(s[4 * b]), ex2(s[4 * b + 1]));
        p[2 * b + 1] = pack2(ex2(s[4 * b + 2]), ex2(s[4 * b + 3]));
      }
    }
  } else {
    float m0 = mx[0], m1 = mx[1];
#pragma unroll
    for (int b = 0; b < 8; b++) {
      m0 = fmaxf(m0, fmaxf(s[4 * b], s[4 * b + 1]));
      m1 = fmaxf(m1, fmaxf(s[4 * b + 2], s[4 * b + 3]));
    }
    m0 = fmaxf(m0, __shfl_xor_sync(0xffffffffu, m0, 1)); m0 = fmaxf(m0, __shfl_xor_sync(0xffffffffu, m0, 2));
    m1 = fmaxf(m1, __shfl_xor_sync(0xffffffffu, m1, 1)); m1 = fmaxf(m1, __shfl_xor_sync(0xffffffffu, m1, 2));
    const float e0 = (m0 == -INFINITY) ? 0.f : m0, e1 = (m1 == -INFINITY) ? 0.f : m1;
    const float c0 = ex2(mx[0] - e0), c1 = ex2(mx[1] - e1);
    mx[0] = m0; mx[1] = m1;
#pragma unroll
    for (int b = 0; b < 3; b++) { o[4 * b] *= c0; o[4 * b + 1] *= c0; o[4 * b + 2] *= c1; o[4 * b + 3] *= c1; }
#pragma unroll
    for (int b = 0; b < 8; b++) {
      p[2 * b] = pack2(ex2(s[4 * b] - e0), ex2(s[4 * b + 1] - e0));
      p[2 * b + 1] = pack2(ex2(s[4 * b + 2] - e1), ex2(s[4 * b + 3] - e1));
    }
  }
  fence_regs(p); fence_regs(o);
  wg_fence();
#pragma unroll
  for (int k = 0; k < 4; k++) wgmma_rs_n24_tb1(o, p[4 * k], p[4 * k + 1], p[4 * k + 2], p[4 * k + 3], vd + k * 96, 1);
  wg_commit();
  wg_wait<0>(); fence_regs(o);
}

__device__ __forceinline__ int fresh_tid() { int v; asm volatile("mov.u32 %0, %%tid.x;" : "=r"(v)); return v; }
__device__ __forceinline__ int cm_woff(int cc) { return (cc >> 3) * 32 + ((cc & 7) >> 1); }

__device__ __forceinline__ void q_load(uint32_t (&q)[8], int pass) {
  const int td = fresh_tid(), ln = td & 31, tt = ln & 3;
  const int col = (pass * 16 + (td >> 5)) * DH + 2 * tt;
  const uint32_t* q0 = (const uint32_t*)g_q + (size_t)(cta_mb() * 4 + cta_j()) * 2 * NC_Q * 32 + (ln >> 2) * 4;
  const uint32_t* q1 = q0 + NC_Q * 32;
  q[0] = __ldcg(q0 + cm_woff(col)); q[1] = __ldcg(q1 + cm_woff(col));
  q[2] = __ldcg(q0 + cm_woff(col + 8)); q[3] = __ldcg(q1 + cm_woff(col + 8));
  q[4] = tt < 2 ? __ldcg(q0 + cm_woff(col + 16)) : 0u; q[5] = tt < 2 ? __ldcg(q1 + cm_woff(col + 16)) : 0u;
}
template <bool FAST>
__device__ __forceinline__ void att_run(const uint32_t (&q)[8], float (&o)[12], float (&mx)[2], uint32_t sb, int pass, uint32_t m16) {
  static_assert(AT_ST == 3, "ring schedule");
  constexpr int SS = AT_STAGE / 16;
  const uint32_t a4 = ((sb & 0x3FFFFu) + OFF_AT) >> 4;
  const uint64_t kd = mk64(a4 | (8u << 16), 48u);
  const uint64_t vd = mk64((a4 + 24) | (48u << 16), 8u);
  const uint32_t fa = sb + OFF_BAR + B_AFULL;
  uint32_t ea;
  asm volatile("mapa.shared::cluster.u32 %0, %1, %2;" : "=r"(ea) : "r"(sb + OFF_BAR + B_AEMPTY), "r"(threadIdx.x & 1));
  const bool sig = (threadIdx.x & 31) < 2;
  fence_regs(o);
  if (FAST) {
    uint32_t ph = pass;
    auto stage = [&](int st) {
      uint64_t k2, v2;
      asm volatile("mov.b64 %0, {%1, %2};" : "=l"(k2) : "r"(a4 | (8u << 16)), "n"(48));
      asm volatile("mov.b64 %0, {%1, %2};" : "=l"(v2) : "r"((a4 + 24) | (48u << 16)), "n"(8));
      mbar_wait(fa + 8 * st, ph);
      att_tile<true>(q, o, mx, k2 + st * SS, v2 + st * SS, m16);
      att_tile<true>(q, o, mx, k2 + st * SS + 384, v2 + st * SS + 384, m16);
      if (sig) asm volatile("mbarrier.arrive.shared::cluster.b64 _, [%0];" ::"r"(ea + 8 * st) : "memory");
    };
#pragma unroll 1
    for (int lap = 0;; lap++) {
      if (lap > 0 || pass == 0) {
        stage(0);
        if (lap == 5 && pass == 0) break;
      }
      stage(1);
      if (lap == 5) break;
      stage(2);
      ph ^= 1;
    }
  } else {
    int st = pass, ph = pass;
#pragma unroll 1
    for (int c = 0; c < 32; c++) {
      if (!(c & 1)) mbar_wait(fa + 8 * st, ph);
      att_tile<false>(q, o, mx, kd + st * SS + (c & 1) * 384, vd + st * SS + (c & 1) * 384, m16);
      if (c & 1) {
        if (sig) asm volatile("mbarrier.arrive.shared::cluster.b64 _, [%0];" ::"r"(ea + 8 * st) : "memory");
        if (++st == AT_ST) { st = 0; ph ^= 1; }
      }
    }
  }
}

template <int N>
__device__ __forceinline__ void head_gemm(float (&acc)[N / 2], uint32_t sb, uint32_t boff, uint32_t blo, uint32_t bhi,
                                          int kstep1, int kstep2, int kbstep, bool stage_rel) {
  const uint32_t lane = threadIdx.x & 31, sb4 = (sb & 0x3FFFFu) >> 4;
#pragma unroll
  for (int i = 0; i < N / 2; i++) acc[i] = 0.f;
  fence_regs(acc);
#pragma unroll 1
  for (int it = 0; it < 10; it++) {
    const int s = it >= G_ST ? it - G_ST : it;
    mbar_wait(sb + OFF_BAR + B_HFULL + 8 * s, it >= G_ST ? 1 : 0);
    const uint32_t sa = sb4 + s * (G_STAGE / 16);
    const uint64_t da = mk64(sa | DSwzA::LO, DSwzA::HI);
    const uint64_t db = mk64(((stage_rel ? sa : sb4) + boff + it * kbstep) | blo, bhi);
    wg_fence();
#pragma unroll
    for (int k = 0; k < 4; k++) WG<N>::mma(acc, da + 2 * k, db + (k >> 1) * kstep2 + (k & 1) * kstep1, (it | k) ? 1 : 0);
    wg_commit();
    wg_wait<0>();
    mbar_arrive_pair(sb + OFF_BAR + B_HEMPTY + 8 * s, lane);
  }
  fence_regs(acc);
}
template <int NB>
__device__ __forceinline__ void q_store(const float* acc, int rg, int core0, int lane) {
  uint32_t* q0 = (uint32_t*)g_q + ((size_t)rg * NC_Q + core0) * 32 + lane;
#pragma unroll
  for (int b = 0; b < NB; b++) {
    q0[b * 32] = pack2(acc[4 * b] * QSCALE, acc[4 * b + 1] * QSCALE);
    q0[b * 32 + NC_Q * 32] = pack2(acc[4 * b + 2] * QSCALE, acc[4 * b + 3] * QSCALE);
  }
}

__device__ __forceinline__ void attn_role(uint32_t sb, unsigned char* sm, uint32_t m16) {
  const int tid = threadIdx.x, wg = __shfl_sync(0xffffffffu, tid >> 7, 0), w = (tid >> 5) & 3, lane = tid & 31;
  const int mb = cta_mb(), j = cta_j();
  {
    const int g = lane >> 2, t = lane & 3;
    const int rg = mb * 8 + w * 2;
    if (wg < 2) {
      float acc[32];
      head_gemm<64>(acc, sb, H_WQ / 16 + wg * 256, 256u << 16, 64u | (1u << 30), 128, 512, 0, true);
      q_store<8>(acc, rg, (tile160_c0(j) >> 3) + wg * 8, lane);
      ev_arrive(sb, E_Q);
    } else if (wg == 2) {
      float acc[48];
      head_gemm<96>(acc, sb, H_HALF / 16, 128u << 16, 32u | (2u << 30), 64, 384, 0, true);
      q_store<4>(acc, rg, tile160_ch(j) >> 3, lane);
      ev_arrive(sb, E_Q);
      float st[4] = {0.f, 0.f, 0.f, 0.f};
      if (j != 3) {
        uint4* hs = (uint4*)(sm + OFF_HS) + (tid & 127);
        uint32_t* z1h = (uint32_t*)g_z1 + ((size_t)rg * NC_Z + (ztile_ch(j) >> 3)) * 32 + lane;
#pragma unroll
        for (int i = 0; i < 2; i++)
          hs[i * 128] = gelu8(acc[16 + 8 * i], acc[17 + 8 * i], acc[18 + 8 * i], acc[19 + 8 * i], acc[20 + 8 * i], acc[21 + 8 * i], acc[22 + 8 * i], acc[23 + 8 * i], st);
#pragma unroll
        for (int b = 0; b < 4; b++) {
          z1h[b * 32] = pack2(acc[32 + 4 * b], acc[33 + 4 * b]);
          z1h[b * 32 + NC_Z * 32] = pack2(acc[34 + 4 * b], acc[35 + 4 * b]);
        }
      }
      ln_partial(sm, 1, st, tid);
      ev_arrive(sb, E_S0D);
    } else {
      if (j < 2) {
#pragma unroll 1
        for (int it = 0; it < 10; it++) {
          const int s = it >= G_ST ? it - G_ST : it;
          mbar_wait(sb + OFF_BAR + B_HFULL + 8 * s, it >= G_ST ? 1 : 0);
          mbar_arrive_pair(sb + OFF_BAR + B_HEMPTY + 8 * s, lane);
        }
      } else {
        float acc2[12];
        bar_sync(6, 640);
        head_gemm<24>(acc2, sb, OFF_KVW / 16, 24u << 16, 8u, 48, 96, 192, false);
        const bool isk = j == 2;
        uint32_t v[6];
#pragma unroll
        for (int i = 0; i < 6; i++) v[i] = pack2(acc2[2 * i], acc2[2 * i + 1]);
        {
          const uint32_t cp = t == 2 ? ((g & 1) ? 0x3F813F80u : 0x3F803F80u) : ((g & 1) ? 0xBDB3436Fu : 0xBDB342FDu), cn = t == 2 ? 0x00003F80u : 0u;
          constexpr uint32_t PM = (is_poly_blk(0) ? 1 : 0) | (is_poly_blk(1) ? 2 : 0) | (is_poly_blk(2) ? 4 : 0) | (is_poly_blk(3) ? 8 : 0) |
                                  (is_poly_blk(4) ? 16 : 0) | (is_poly_blk(5) ? 32 : 0) | (is_poly_blk(6) ? 64 : 0) | (is_poly_blk(7) ? 128 : 0);
          const uint32_t pm = isk ? PM >> (2 * w) : 0u;
          uint32_t* dst = (uint32_t*)(g_kv + (size_t)rg * 384 + (isk ? 0 : 192)) + lane;
          dst[0] = v[0]; dst[192] = v[1]; dst[32] = v[2]; dst[224] = v[3];
          dst[64] = t < 2 ? v[4] : ((pm & 1) ? cp : cn);
          dst[256] = t < 2 ? v[5] : ((pm & 2) ? cp : cn);
          if (!isk && t == 2) {
            g_gate[mb * 64 + w * 16 + g] = rcp(1.f + ex2(-acc2[8] * 1.4426950408889634f));
            g_gate[mb * 64 + w * 16 + g + 8] = rcp(1.f + ex2(-acc2[10] * 1.4426950408889634f));
          }
        }
        if (t >= 2) { v[4] = 0u; v[5] = 0u; }
        float mx = 0.f;
#pragma unroll
        for (int r = 0; r < 2; r++) {
          float kn = 0.f, va = 0.f;
#pragma unroll
          for (int b = 0; b < 3; b++) {
            const float x0 = bf_lo(v[2 * b + r]), x1 = bf_hi(v[2 * b + r]);
            kn += x0 * x0 + x1 * x1;
            va = nanmax(nanmax(va, fabsf(x0)), fabsf(x1));
          }
          kn += __shfl_xor_sync(0xffffffffu, kn, 1);
          kn += __shfl_xor_sync(0xffffffffu, kn, 2);
          mx = nanmax(mx, isk ? kn : va);
        }
        const uint32_t mxw = __reduce_max_sync(0xffffffffu, __float_as_uint(mx) & 0x7FFFFFFFu);
        if (lane == 0) atomicMax(g_flags + F_KV * 32 + (isk ? 1 : 2), mxw);
      }
      ev_arrive(sb, E_Q);
    }
  }
  uint32_t q[8];
  mbar_wait(sb + OFF_BAR + B_EV + 8 * E_GO, 0);
  q_load(q, 0);
#pragma unroll 1
  for (int pass = 0; pass < 2; pass++) {
    uint32_t allok = 0;
    float o[12], mx[2] = {-INFINITY, -INFINITY};
#pragma unroll
    for (int i = 0; i < 12; i++) o[i] = 0.f;
    {
      const int td = fresh_tid(), tt = td & 3;
      const float4 bc = *(const float4*)(sm + OFF_BC);
      const float kmax = bc.x;
      const int ev = (int)(__float_as_uint(bc.y) >> 23) - 127;
      const float xhi = (float)min(113, 113 - ev), xlo = (float)max(-125, -102 - ev);
      q[6] = __float_as_uint(bc.z); q[7] = __float_as_uint(bc.w);
      float n0 = bf_lo(q[0]) * bf_lo(q[0]) + bf_hi(q[0]) * bf_hi(q[0]) + bf_lo(q[2]) * bf_lo(q[2]) + bf_hi(q[2]) * bf_hi(q[2]) +
                 bf_lo(q[4]) * bf_lo(q[4]) + bf_hi(q[4]) * bf_hi(q[4]);
      float n1 = bf_lo(q[1]) * bf_lo(q[1]) + bf_hi(q[1]) * bf_hi(q[1]) + bf_lo(q[3]) * bf_lo(q[3]) + bf_hi(q[3]) * bf_hi(q[3]) +
                 bf_lo(q[5]) * bf_lo(q[5]) + bf_hi(q[5]) * bf_hi(q[5]);
      n0 += __shfl_xor_sync(0xffffffffu, n0, 1); n0 += __shfl_xor_sync(0xffffffffu, n0, 2);
      n1 += __shfl_xor_sync(0xffffffffu, n1, 1); n1 += __shfl_xor_sync(0xffffffffu, n1, 2);
      const float b0 = ceilf(sqrt_a(n0 * kmax) * 1.001f + 0.01f), b1 = ceilf(sqrt_a(n1 * kmax) * 1.001f + 0.01f);
      const bool ok = (2.f * b0 <= xhi - xlo) && (2.f * b1 <= xhi - xlo);
      asm volatile("{\n.reg .pred p, q;\nsetp.ne.u32 p, %1, 0;\nbarrier.cta.red.and.aligned.pred q, %2, 128, p;\nselp.u32 %0, 1, 0, q;\n}"
                   : "=r"(allok) : "r"((uint32_t)ok), "r"((td >> 7) + 1) : "memory");
      allok = __shfl_sync(0xffffffffu, allok, 0);
      if (allok) {
        if (tt == 2) { q[4] = pack2(xhi - b0, 98304.f); q[5] = pack2(xhi - b1, 98304.f); }
        if (tt == 3) { q[4] = 0x3F803F80u; q[5] = 0x3F803F80u; }
      }
      fence_regs(q);
    }
    if (allok) att_run<true>(q, o, mx, sb, pass, m16);
    else att_run<false>(q, o, mx, sb, pass, m16);
    if (pass == 0) { q_load(q, 1); mbar_wait(sb + OFF_BAR + B_EV + 8 * E_BC, 0); }
    {
      const int td = fresh_tid(), wq_ = td >> 5, ln = td & 31, gg = ln >> 2, tt = ln & 3;
      const int col = (pass * 16 + wq_) * DH + 2 * tt;
      const float l0 = __shfl_sync(0xffffffffu, o[8], (ln & ~3) | 2), l1 = __shfl_sync(0xffffffffu, o[10], (ln & ~3) | 2);
      const int tb = cta_mb() * 4 + cta_j();
      const float f0 = ((const float*)(sm + OFF_BC))[4 + gg], f1 = ((const float*)(sm + OFF_BC))[12 + gg];
      const float r0 = rcp(l0), r1 = rcp(l1);
#pragma unroll
      for (int b = 0; b < 3; b++) { o[4 * b] *= r0; o[4 * b + 1] *= r0; o[4 * b + 2] *= r1; o[4 * b + 3] *= r1; }
      uint32_t* o0 = (uint32_t*)g_au + (size_t)tb * 2 * NC_AU * 32 + gg * 4;
      uint32_t* o1 = o0 + NC_AU * 32;
      o0[cm_woff(col)] = pack2(o[0] * f0, o[1] * f0);         o1[cm_woff(col)] = pack2(o[2] * f1, o[3] * f1);
      o0[cm_woff(col + 8)] = pack2(o[4] * f0, o[5] * f0);     o1[cm_woff(col + 8)] = pack2(o[6] * f1, o[7] * f1);
      if (tt < 2) { o0[cm_woff(col + 16)] = pack2(o[8] * f0, o[9] * f0); o1[cm_woff(col + 16)] = pack2(o[10] * f1, o[11] * f1); }
      ev_arrive(sb, pass ? E_O1 : E_O0);
    }
  }
}

__global__ void __cluster_dims__(2, 1, 1) __launch_bounds__(768, 1)
k_mega(const __grid_constant__ Maps maps, const bf16* __restrict__ wk, const bf16* __restrict__ wv,
       const bf16* __restrict__ gate_w, const bf16* __restrict__ b_sp, bf16* __restrict__ out) {
  extern __shared__ __align__(1024) unsigned char sm[];
  const uint32_t sb = __shfl_sync(0xffffffffu, smem_u32(sm), 0);
  {
    const int wi = __shfl_sync(0xffffffffu, (int)(threadIdx.x >> 5), 0);
    if (2 * wi < NBAR && elect_one()) {
#pragma unroll
      for (int h = 0; h < 2; h++) {
        const int i = 2 * wi + h;
        mbar_init(sb + OFF_BAR + 8 * i, (int)((BAR_CNT[i >> 3] >> ((i & 7) * 8)) & 0xFF));
      }
      fence_barrier_init();
    }
    __syncwarp();
    asm volatile("barrier.cluster.arrive.relaxed.aligned;" ::: "memory");
    if (cta_j() >= 2 && wi < 20) {
      const int k = threadIdx.x;
      const uint2* src = (const uint2*)(cta_j() == 2 ? wk : wv) + k * 5;
      const uint2 a0 = src[0], a1 = src[1], a2 = src[2], a3 = src[3], a4 = src[4];
      const uint32_t gw = cta_j() == 3 ? (uint32_t)__bfloat16_as_ushort(gate_w[k]) : 0u;
      uint4* dst = (uint4*)(sm + OFF_KVW + (k >> 3) * 384 + (k & 7) * 16);
      dst[0]  = make_uint4(a0.x, a0.y, a1.x, a1.y);
      dst[8]  = make_uint4(a2.x, a2.y, a3.x, a3.y);
      dst[16] = make_uint4(a4.x, a4.y, gw, 0);
      fence_proxy_async();
      if ((wi >> 2) != 3) asm volatile("bar.arrive 6, 640;" ::: "memory");
    }
    if (wi == 22 && (threadIdx.x & 31) < 13) asm volatile("prefetch.tensormap [%0];" ::"l"(&maps.x + (threadIdx.x & 31)) : "memory");
    __syncwarp();
    asm volatile("barrier.cluster.wait.aligned;" ::: "memory");
  }
  const int wgid = __shfl_sync(0xffffffffu, (int)(threadIdx.x >> 7), 0);
  if (wgid < 4) {
    attn_role(sb, sm, maps.m16);
    cluster_sync();
  } else if (wgid == 4) {
    asm volatile("setmaxnreg.inc.sync.aligned.u32 136;");
    gemm_role(sb, sm, b_sp, out);
    __syncwarp();
    asm volatile("barrier.cluster.wait.aligned;" ::: "memory");
  } else {
    asm volatile("setmaxnreg.dec.sync.aligned.u32 24;");
    service_role(maps, sb, sm);
    __syncwarp();
    cluster_sync();
  }
}

typedef CUresult (*EncodeFn)(CUtensorMap*, CUtensorMapDataType, cuuint32_t, void*, const cuuint64_t*, const cuuint64_t*,
                             const cuuint32_t*, const cuuint32_t*, CUtensorMapInterleave, CUtensorMapSwizzle,
                             CUtensorMapL2promotion, CUtensorMapFloatOOBfill);

static void make_map2(EncodeFn enc, CUtensorMap* tm, const void* base, uint64_t cols, uint64_t rows, uint32_t nch, uint32_t brows) {
  cuuint64_t gd[3] = {64, rows, cols / 64}; cuuint64_t gs[2] = {cols * 2, 128};
  cuuint32_t bx[3] = {64, brows, nch}; cuuint32_t es[3] = {1, 1, 1};
  enc(tm, CU_TENSOR_MAP_DATA_TYPE_BFLOAT16, 3, (void*)base, gd, gs, bx, es, CU_TENSOR_MAP_INTERLEAVE_NONE,
      CU_TENSOR_MAP_SWIZZLE_128B, CU_TENSOR_MAP_L2_PROMOTION_L2_128B, CU_TENSOR_MAP_FLOAT_OOB_FILL_NONE);
}
static void make_map_half(EncodeFn enc, CUtensorMap* tm, const void* base, uint64_t cols, uint64_t rows, bool compact) {
  cuuint64_t gd[3] = {32, rows, cols / 32}; cuuint64_t gs[2] = {cols * 2, 64};
  cuuint32_t bx[3] = {compact ? 32u : 64u, 32, 1}; cuuint32_t es[3] = {1, 1, 1};
  enc(tm, CU_TENSOR_MAP_DATA_TYPE_BFLOAT16, 3, (void*)base, gd, gs, bx, es, CU_TENSOR_MAP_INTERLEAVE_NONE,
      compact ? CU_TENSOR_MAP_SWIZZLE_64B : CU_TENSOR_MAP_SWIZZLE_128B, CU_TENSOR_MAP_L2_PROMOTION_L2_128B, CU_TENSOR_MAP_FLOAT_OOB_FILL_NONE);
}
static void make_map_cm(EncodeFn enc, CUtensorMap* tm, const void* base, uint64_t nc, uint32_t boxcores, uint32_t boxrg) {
  cuuint64_t gd[3] = {64, nc, (cuuint64_t)(S_ / 8)}; cuuint64_t gs[2] = {128, nc * 128};
  cuuint32_t bx[3] = {64, boxcores, boxrg}; cuuint32_t es[3] = {1, 1, 1};
  enc(tm, CU_TENSOR_MAP_DATA_TYPE_BFLOAT16, 3, (void*)base, gd, gs, bx, es, CU_TENSOR_MAP_INTERLEAVE_NONE,
      CU_TENSOR_MAP_SWIZZLE_NONE, CU_TENSOR_MAP_L2_PROMOTION_L2_128B, CU_TENSOR_MAP_FLOAT_OOB_FILL_NONE);
}

extern "C" void kernel_launch(void* const* d_in, const int* in_sizes, int n_in, void* d_out, int out_size) {
  const bf16* x = (const bf16*)d_in[0];
  const bf16* wq = (const bf16*)d_in[1];
  const bf16* wk = (const bf16*)d_in[2];
  const bf16* wv = (const bf16*)d_in[3];
  const bf16* wo = (const bf16*)d_in[4];
  const bf16* w_in = (const bf16*)d_in[6];
  const bf16* w_sp = (const bf16*)d_in[7];
  const bf16* b_sp = (const bf16*)d_in[8];
  const bf16* w_out = (const bf16*)d_in[9];
  const bf16* gate_w = (const bf16*)d_in[10];
  bf16* out = (bf16*)d_out;

  void* fn = nullptr; cudaDriverEntryPointQueryResult qr;
  cudaGetDriverEntryPoint("cuTensorMapEncodeTiled", &fn, cudaEnableDefault, &qr);
  EncodeFn enc = (EncodeFn)fn;
  void *p_z1, *p_z2, *p_au;
  cudaGetSymbolAddress(&p_z1, g_z1);
  cudaGetSymbolAddress(&p_z2, g_z2);
  cudaGetSymbolAddress(&p_au, g_au);
  Maps m;
  make_map2(enc, &m.x, x, D_, S_, 1, 64);
  make_map2(enc, &m.wq, wq, D_, D_, 2, 32);
  make_map_half(enc, &m.wqh, wq, D_, D_, true);
  make_map2(enc, &m.win, w_in, 2 * FH, D_, 3, 32);
  make_map_half(enc, &m.winh, w_in, 2 * FH, D_, true);
  make_map2(enc, &m.wsp, w_sp, S_, S_, 1, 64);
  make_map_cm(enc, &m.z1, p_z1, NC_Z, 27, 8);
  make_map_cm(enc, &m.z2, p_z2, NC_Z, 27, 4);
  make_map_cm(enc, &m.au, p_au, NC_AU, 8, 8);
  make_map2(enc, &m.wo, wo, D_, D_, 2, 32);
  make_map_half(enc, &m.woh, wo, D_, D_, false);
  make_map2(enc, &m.wout, w_out, D_, FH, 2, 32);
  make_map_half(enc, &m.wouth, w_out, D_, FH, false);

  const void* pf[6] = {x, wq, w_in, w_sp, wo, w_out};
  const uint32_t pfb[6] = {S_ * D_ * 2, D_ * D_ * 2, D_ * 2 * FH * 2, S_ * S_ * 2, D_ * D_ * 2, FH * D_ * 2};
  for (int i = 0; i < 6; i++) { m.pf_ptr[i] = pf[i]; m.pf_chunk[i] = pfb[i] / 128; }

  m.m16 = 65536u;
  cudaFuncSetAttribute(k_mega, cudaFuncAttributeMaxDynamicSharedMemorySize, SMEM_BYTES);
  cudaLaunchConfig_t cfg = {};
  cfg.gridDim = dim3(128); cfg.blockDim = dim3(768); cfg.dynamicSmemBytes = SMEM_BYTES; cfg.stream = 0;
  cudaLaunchAttribute at[1];
  at[0].id = cudaLaunchAttributeCooperative; at[0].val.cooperative = 1;
  cfg.attrs = at; cfg.numAttrs = 1;
  static bool coop = true;
  if (!coop || cudaLaunchKernelEx(&cfg, k_mega, m, wk, wv, gate_w, b_sp, out) != cudaSuccess) {
    (void)cudaGetLastError();
    coop = false;
    k_mega<<<128, 768, SMEM_BYTES>>>(m, wk, wv, gate_w, b_sp, out);
  }
}
```
